```python
import torch

def _softmax(x, axis=-1):
    return torch.softmax(x, dim=axis)

def _gelu(x):
    return torch.nn.functional.gelu(x, approximate='tanh')

def _silu(x):
    return torch.nn.functional.silu(x)

def _sigmoid(x):
    return torch.sigmoid(x)

def _layernorm(x, axis=-1, eps=1e-05):
    m = x.mean(dim=axis, keepdim=True)
    v = x.var(dim=axis, keepdim=True, unbiased=False)
    return (x - m) / torch.sqrt(v + eps)

def _scatter_add(tgt, idx, src, axis=0):
    return tgt.clone().index_add_(axis, idx, src)

def _segment_sum(src, seg, n):
    out = torch.zeros((n,) + src.shape[1:], dtype=src.dtype)
    return out.index_add_(0, seg, src)

def _pad(x, pw):
    flat = tuple((v for pair in reversed(pw) for v in pair))
    return torch.nn.functional.pad(x, flat)
kernel_name = 'standalone__tree_speculative_verify_tree_attention_over_candidate_token_tree__sampling'

def setup_inputs():

    _w = lambda a: (lambda t: t.to(torch.bfloat16) if t.is_floating_point() else t)(torch.as_tensor(a))
    B, Hq, Hkv, T, C, D = (8, 32, 8, 8, 4096, 128)
    tree_mask = torch.zeros((B, T, T), dtype=float)
    for b in range(B):
        parent = torch.zeros(T, dtype=torch.int64)
        for i in range(1, T):
            parent[i] = int(torch.randint(0, i, (1,)).item())
        for i in range(T):
            j = i
            tree_mask[b, i, j] = 1.0
            while j > 0:
                j = parent[j]
                tree_mask[b, i, j] = 1.0
    return {'q': _w((lambda *s: torch.randn(*s, dtype=torch.bfloat16) * 0.8)(B, Hq, T, D)), 'k_cache': _w((lambda *s: torch.randn(*s, dtype=torch.bfloat16) * 0.8)(B, Hkv, C, D)), 'v_cache': _w((lambda *s: torch.randn(*s, dtype=torch.bfloat16) * 0.05)(B, Hkv, C, D)), 'k_tree': _w((lambda *s: torch.randn(*s, dtype=torch.bfloat16) * 0.8)(B, Hkv, T, D)), 'v_tree': _w((lambda *s: torch.randn(*s, dtype=torch.bfloat16) * 0.05)(B, Hkv, T, D)), 'tree_mask': _w(tree_mask)}

def reference(q, k_cache, v_cache, k_tree, v_tree, tree_mask):
    B, Hq, T, D = q.shape
    Hkv, C = (k_cache.shape[1], k_cache.shape[2])
    rep = Hq // Hkv
    kc = (lambda x, n, axis: torch.repeat_interleave(x, n, dim=axis))(k_cache, rep, axis=1)
    vc = (lambda x, n, axis: torch.repeat_interleave(x, n, dim=axis))(v_cache, rep, axis=1)
    kt = (lambda x, n, axis: torch.repeat_interleave(x, n, dim=axis))(k_tree, rep, axis=1)
    vt = (lambda x, n, axis: torch.repeat_interleave(x, n, dim=axis))(v_tree, rep, axis=1)
    k = torch.concatenate([kc, kt], axis=2)
    v = torch.concatenate([vc, vt], axis=2)
    scale = D ** (-0.5)
    scores = torch.einsum('bhqd,bhkd->bhqk', q, k) * scale
    ctx_mask = torch.ones((B, 1, T, C), dtype=scores.dtype)
    tm = tree_mask[:, None, :, :].clone()
    full_mask = torch.concatenate([ctx_mask, tm], axis=-1)
    scores = scores + (1.0 - full_mask) * -1000000000.0
    p = _softmax(scores, axis=-1)
    return torch.einsum('bhqk,bhkd->bhqd', p, v)
```

```cpp
#include <cuda_runtime.h>
#include <cuda_bf16.h>
#include <cuda.h>
#include <stdint.h>

namespace {

constexpr int B_ = 8, HQ = 32, HKV = 8, T_ = 8, C_ = 4096, D_ = 128;
constexpr int REP = HQ / HKV;
constexpr int ROWS = REP * T_;
constexpr int NWARPS = 8;
constexpr int NTHREADS = NWARPS * 32;
constexpr int R_ = 16;
constexpr int STAGES = 3;
constexpr int HALF_BYTES = R_ * 128;
constexpr int TILE_BYTES = 2 * HALF_BYTES;
constexpr int STAGE_BYTES = 2 * TILE_BYTES;
constexpr int KEYS_PER_CTA = C_ / 2;
constexpr int TILES_PER_WARP = KEYS_PER_CTA / R_ / NWARPS;
constexpr int WARP_RING = STAGES * STAGE_BYTES;

constexpr int OFF_RING = 0;
constexpr int OFF_Q = OFF_RING + NWARPS * WARP_RING;
constexpr int OFF_TREE = OFF_Q + ROWS * 256;
constexpr int OFF_XO = OFF_TREE + STAGE_BYTES;
constexpr int OFF_XML = OFF_XO + 16 * 128 * 4;
constexpr int OFF_ML = OFF_XML + 16 * 2 * 4;
constexpr int OFF_BAR = OFF_ML + NWARPS * ROWS * 2 * 4;
constexpr int SMEM_BYTES = OFF_BAR + NWARPS * STAGES * 8;

__device__ __forceinline__ uint32_t smem_u32(const void* p) { return (uint32_t)__cvta_generic_to_shared(p); }
__device__ __forceinline__ void mbar_init(uint32_t bar, int cnt) {
    asm volatile("mbarrier.init.shared::cta.b64 [%0], %1;" ::"r"(bar), "r"(cnt));
}
__device__ __forceinline__ void mbar_expect_tx(uint32_t bar, uint32_t bytes) {
    asm volatile("mbarrier.arrive.expect_tx.shared::cta.b64 _, [%0], %1;" ::"r"(bar), "r"(bytes) : "memory");
}
__device__ __forceinline__ void mbar_wait(uint32_t bar, uint32_t parity) {
    asm volatile(
        "{\n"
        ".reg .pred p;\n"
        "WAIT_%=:\n"
        "mbarrier.try_wait.parity.shared::cta.b64 p, [%0], %1;\n"
        "@p bra DONE_%=;\n"
        "bra WAIT_%=;\n"
        "DONE_%=:\n"
        "}\n" ::"r"(bar), "r"(parity) : "memory");
}
__device__ __forceinline__ void tma_load_2d(uint32_t dst, const CUtensorMap* map, int c0, int c1, uint32_t bar) {
    asm volatile(
        "cp.async.bulk.tensor.2d.shared::cluster.global.mbarrier::complete_tx::bytes [%0], [%1, {%3, %4}], [%2];"
        ::"r"(dst), "l"(map), "r"(bar), "r"(c0), "r"(c1) : "memory");
}
__device__ __forceinline__ void ldsm_x4(uint32_t addr, uint32_t& r0, uint32_t& r1, uint32_t& r2, uint32_t& r3) {
    asm volatile("ldmatrix.sync.aligned.m8n8.x4.shared.b16 {%0,%1,%2,%3}, [%4];"
                 : "=r"(r0), "=r"(r1), "=r"(r2), "=r"(r3) : "r"(addr) : "memory");
}
__device__ __forceinline__ void ldsm_x4_t(uint32_t addr, uint32_t& r0, uint32_t& r1, uint32_t& r2, uint32_t& r3) {
    asm volatile("ldmatrix.sync.aligned.m8n8.x4.trans.shared.b16 {%0,%1,%2,%3}, [%4];"
                 : "=r"(r0), "=r"(r1), "=r"(r2), "=r"(r3) : "r"(addr) : "memory");
}
__device__ __forceinline__ void mma16816(float (&c)[4], uint32_t a0, uint32_t a1, uint32_t a2, uint32_t a3,
                                         uint32_t b0, uint32_t b1) {
    asm volatile(
        "mma.sync.aligned.m16n8k16.row.col.f32.bf16.bf16.f32 {%0,%1,%2,%3}, {%4,%5,%6,%7}, {%8,%9}, {%0,%1,%2,%3};"
        : "+f"(c[0]), "+f"(c[1]), "+f"(c[2]), "+f"(c[3])
        : "r"(a0), "r"(a1), "r"(a2), "r"(a3), "r"(b0), "r"(b1));
}
__device__ __forceinline__ float ex2(float x) {
    float y;
    asm("ex2.approx.ftz.f32 %0, %1;" : "=f"(y) : "f"(x));
    return y;
}
__device__ __forceinline__ uint32_t pack_bf16(float lo, float hi) {
    uint32_t r;
    asm("cvt.rn.bf16x2.f32 %0, %1, %2;" : "=r"(r) : "f"(hi), "f"(lo));
    return r;
}

struct WarpState {
    float o[2][16][4];
    float m[2][2];
    float l[2][2];
};

template <bool TREE>
__device__ __forceinline__ void step(WarpState& st, uint32_t qbase, uint32_t kbase, uint32_t vbase, int lane,
                                     const __nv_bfloat16* __restrict__ mask_b) {
    const float scale = 0.08838834764831845f;
    const float log2e = 1.4426950408889634f;
    const int l7 = lane & 7;
    float s[2][2][4];
#pragma unroll
    for (int mt = 0; mt < 2; mt++)
#pragma unroll
        for (int nt = 0; nt < 2; nt++)
#pragma unroll
            for (int i = 0; i < 4; i++) s[mt][nt][i] = 0.f;
    {
        const uint32_t krow = kbase + (l7 + ((lane >> 4) << 3)) * 128;
        const uint32_t kx = (((lane >> 3) & 1) ^ l7);
        const uint32_t qrow = qbase + (l7 + (((lane >> 3) & 1) << 3)) * 128;
        const uint32_t qx = ((lane >> 4) ^ l7);
#pragma unroll
        for (int ks = 0; ks < 8; ks++) {
            uint32_t b0, b1, b2, b3;
            ldsm_x4(krow + (ks >> 2) * HALF_BYTES + ((kx ^ (2 * (ks & 3))) << 4), b0, b1, b2, b3);
#pragma unroll
            for (int mt = 0; mt < 2; mt++) {
                uint32_t a0, a1, a2, a3;
                ldsm_x4(qrow + (ks >> 2) * (ROWS * 128) + mt * 16 * 128 + ((qx ^ (2 * (ks & 3))) << 4), a0, a1, a2, a3);
                mma16816(s[mt][0], a0, a1, a2, a3, b0, b1);
                mma16816(s[mt][1], a0, a1, a2, a3, b2, b3);
            }
        }
    }
    uint32_t p[2][4];
#pragma unroll
    for (int mt = 0; mt < 2; mt++) {
#pragma unroll
        for (int h = 0; h < 2; h++) {
            float t0, t1, t2, t3;
            if (TREE) {
                const int trow = (lane >> 2);
                const int kc = (lane & 3) * 2;
                float m0 = __bfloat162float(mask_b[trow * T_ + kc]);
                float m1 = __bfloat162float(mask_b[trow * T_ + kc + 1]);
                t0 = (s[mt][0][2 * h] * scale + (1.0f - m0) * -1000000000.0f) * log2e;
                t1 = (s[mt][0][2 * h + 1] * scale + (1.0f - m1) * -1000000000.0f) * log2e;
                t2 = -INFINITY;
                t3 = -INFINITY;
            } else {
                const float c = scale * log2e;
                t0 = s[mt][0][2 * h] * c;
                t1 = s[mt][0][2 * h + 1] * c;
                t2 = s[mt][1][2 * h] * c;
                t3 = s[mt][1][2 * h + 1] * c;
            }
            float mx = fmaxf(fmaxf(t0, t1), fmaxf(t2, t3));
            mx = fmaxf(mx, __shfl_xor_sync(0xffffffffu, mx, 1));
            mx = fmaxf(mx, __shfl_xor_sync(0xffffffffu, mx, 2));
            const float mnew = fmaxf(st.m[mt][h], mx);
            const float alpha = ex2(st.m[mt][h] - mnew);
            st.m[mt][h] = mnew;
            const float p0 = ex2(t0 - mnew), p1 = ex2(t1 - mnew), p2 = ex2(t2 - mnew), p3 = ex2(t3 - mnew);
            st.l[mt][h] = st.l[mt][h] * alpha + ((p0 + p1) + (p2 + p3));
            p[mt][h] = pack_bf16(p0, p1);
            p[mt][2 + h] = pack_bf16(p2, p3);
#pragma unroll
            for (int dc = 0; dc < 16; dc++) {
                st.o[mt][dc][2 * h] *= alpha;
                st.o[mt][dc][2 * h + 1] *= alpha;
            }
        }
    }
    {
        const uint32_t vrow = vbase + (l7 + (((lane >> 3) & 1) << 3)) * 128;
        const uint32_t vx = ((lane >> 4) ^ l7);
#pragma unroll
        for (int dp = 0; dp < 8; dp++) {
            uint32_t b0, b1, b2, b3;
            ldsm_x4_t(vrow + (dp >> 2) * HALF_BYTES + ((vx ^ (2 * (dp & 3))) << 4), b0, b1, b2, b3);
#pragma unroll
            for (int mt = 0; mt < 2; mt++) {
                mma16816(st.o[mt][2 * dp], p[mt][0], p[mt][1], p[mt][2], p[mt][3], b0, b1);
                mma16816(st.o[mt][2 * dp + 1], p[mt][0], p[mt][1], p[mt][2], p[mt][3], b2, b3);
            }
        }
    }
}

__global__ void __cluster_dims__(2, 1, 1) __launch_bounds__(NTHREADS, 1)
tree_attn_kernel(const __grid_constant__ CUtensorMap kmap, const __grid_constant__ CUtensorMap vmap,
                 const __nv_bfloat16* __restrict__ q, const __nv_bfloat16* __restrict__ k_tree,
                 const __nv_bfloat16* __restrict__ v_tree, const __nv_bfloat16* __restrict__ tree_mask,
                 __nv_bfloat16* __restrict__ out) {
    extern __shared__ __align__(1024) uint8_t smem[];
    const uint32_t sb = smem_u32(smem);
    const int tid = threadIdx.x, warp = tid >> 5, lane = tid & 31;
    const int pair = blockIdx.x >> 1;
    const int rank = blockIdx.x & 1;
    const int b = pair / HKV;

    const uint32_t ring = sb + OFF_RING + warp * WARP_RING;
    const uint32_t bars = sb + OFF_BAR + warp * STAGES * 8;
    const int row0 = pair * C_ + rank * KEYS_PER_CTA + warp * R_;

    if (lane == 0) {
#pragma unroll
        for (int s = 0; s < STAGES; s++) mbar_init(bars + 8 * s, 1);
        asm volatile("fence.mbarrier_init.release.cluster;" ::: "memory");
        asm volatile("fence.proxy.async.shared::cta;" ::: "memory");
#pragma unroll
        for (int s = 0; s < STAGES; s++) {
            const uint32_t d = ring + s * STAGE_BYTES;
            const int r = row0 + s * (NWARPS * R_);
            mbar_expect_tx(bars + 8 * s, STAGE_BYTES);
            tma_load_2d(d, &kmap, 0, r, bars + 8 * s);
            tma_load_2d(d + HALF_BYTES, &kmap, 64, r, bars + 8 * s);
            tma_load_2d(d + TILE_BYTES, &vmap, 0, r, bars + 8 * s);
            tma_load_2d(d + TILE_BYTES + HALF_BYTES, &vmap, 64, r, bars + 8 * s);
        }
    }
    asm volatile("barrier.cluster.arrive.relaxed.aligned;" ::: "memory");

    {
        const uint4* qg = reinterpret_cast<const uint4*>(q + (size_t)pair * ROWS * D_);
#pragma unroll
        for (int i = 0; i < 2; i++) {
            const int idx = tid + i * NTHREADS;
            const int r = idx >> 4, c = idx & 15;
            const uint4 v = __ldg(qg + idx);
            *reinterpret_cast<uint4*>(smem + OFF_Q + (c >> 3) * (ROWS * 128) + r * 128 + (((c & 7) ^ (r & 7)) << 4)) = v;
        }
        const int idx = tid;
#pragma unroll
        for (int i = 0; i < 2; i++) {
            const int r = (idx >> 4), c = idx & 15;
            uint4 v = make_uint4(0, 0, 0, 0);
            if (r < T_) {
                const __nv_bfloat16* src = (i == 0 ? k_tree : v_tree) + ((size_t)pair * T_ + r) * D_;
                v = __ldg(reinterpret_cast<const uint4*>(src) + c);
            }
            *reinterpret_cast<uint4*>(smem + OFF_TREE + i * TILE_BYTES + (c >> 3) * HALF_BYTES + r * 128 +
                                      (((c & 7) ^ (r & 7)) << 4)) = v;
        }
    }
    __syncthreads();

    WarpState st;
#pragma unroll
    for (int mt = 0; mt < 2; mt++) {
#pragma unroll
        for (int dc = 0; dc < 16; dc++)
#pragma unroll
            for (int i = 0; i < 4; i++) st.o[mt][dc][i] = 0.f;
        st.m[mt][0] = st.m[mt][1] = -INFINITY;
        st.l[mt][0] = st.l[mt][1] = 0.f;
    }
    const uint32_t qbase = sb + OFF_Q;

    if (rank == 0 && warp == NWARPS - 1) {
        step<true>(st, qbase, sb + OFF_TREE, sb + OFF_TREE + TILE_BYTES, lane, tree_mask + b * T_ * T_);
    }

    {
        int stage = 0;
        uint32_t phase = 0;
#pragma unroll 1
        for (int t = 0; t < TILES_PER_WARP; t++) {
            const uint32_t d = ring + stage * STAGE_BYTES;
            mbar_wait(bars + 8 * stage, phase);
            step<false>(st, qbase, d, d + TILE_BYTES, lane, nullptr);
            __syncwarp();
            if (lane == 0 && t + STAGES < TILES_PER_WARP) {
                const int r = row0 + (t + STAGES) * (NWARPS * R_);
                mbar_expect_tx(bars + 8 * stage, STAGE_BYTES);
                tma_load_2d(d, &kmap, 0, r, bars + 8 * stage);
                tma_load_2d(d + HALF_BYTES, &kmap, 64, r, bars + 8 * stage);
                tma_load_2d(d + TILE_BYTES, &vmap, 0, r, bars + 8 * stage);
                tma_load_2d(d + TILE_BYTES + HALF_BYTES, &vmap, 64, r, bars + 8 * stage);
            }
            if (++stage == STAGES) { stage = 0; phase ^= 1; }
        }
    }

    constexpr int OPITCH = 132;
    {
        float* po = reinterpret_cast<float*>(smem + OFF_RING + warp * WARP_RING);
        float* pml = reinterpret_cast<float*>(smem + OFF_ML) + warp * ROWS * 2;
#pragma unroll
        for (int mt = 0; mt < 2; mt++) {
#pragma unroll
            for (int h = 0; h < 2; h++) {
                const int r = mt * 16 + h * 8 + (lane >> 2);
                float l = st.l[mt][h];
                l += __shfl_xor_sync(0xffffffffu, l, 1);
                l += __shfl_xor_sync(0xffffffffu, l, 2);
                if ((lane & 3) == 0) {
                    pml[r * 2] = st.m[mt][h];
                    pml[r * 2 + 1] = l;
                }
#pragma unroll
                for (int dc = 0; dc < 16; dc++) {
                    *reinterpret_cast<float2*>(po + r * OPITCH + dc * 8 + (lane & 3) * 2) =
                        make_float2(st.o[mt][dc][2 * h], st.o[mt][dc][2 * h + 1]);
                }
            }
        }
    }
    __syncthreads();

    const int crow = tid >> 3, cseg = tid & 7;
    float acc[16];
    float M, L;
    {
        const float* pml = reinterpret_cast<const float*>(smem + OFF_ML);
        float mw[NWARPS];
        M = -INFINITY;
#pragma unroll
        for (int w = 0; w < NWARPS; w++) {
            mw[w] = pml[(w * ROWS + crow) * 2];
            M = fmaxf(M, mw[w]);
        }
        L = 0.f;
#pragma unroll
        for (int i = 0; i < 16; i++) acc[i] = 0.f;
#pragma unroll
        for (int w = 0; w < NWARPS; w++) {
            const float f = ex2(mw[w] - M);
            L += pml[(w * ROWS + crow) * 2 + 1] * f;
            const float* po = reinterpret_cast<const float*>(smem + OFF_RING + w * WARP_RING) + crow * OPITCH;
#pragma unroll
            for (int i = 0; i < 4; i++) {
                const float4 v = *reinterpret_cast<const float4*>(po + i * 32 + cseg * 4);
                acc[4 * i] += v.x * f;
                acc[4 * i + 1] += v.y * f;
                acc[4 * i + 2] += v.z * f;
                acc[4 * i + 3] += v.w * f;
            }
        }
    }
    asm volatile("barrier.cluster.wait.aligned;" ::: "memory");
    const int owner = crow >> 4;
    const int lrow = crow & 15;
    if (owner != rank) {
        uint32_t ra;
        asm volatile("mapa.shared::cluster.u32 %0, %1, %2;" : "=r"(ra) : "r"(sb), "r"(owner));
#pragma unroll
        for (int i = 0; i < 4; i++) {
            asm volatile("st.shared::cluster.v4.f32 [%0], {%1,%2,%3,%4};" ::"r"(ra + OFF_XO + (lrow * 128 + i * 32 + cseg * 4) * 4),
                         "f"(acc[4 * i]), "f"(acc[4 * i + 1]), "f"(acc[4 * i + 2]), "f"(acc[4 * i + 3]) : "memory");
        }
        if (cseg == 0) {
            asm volatile("st.shared::cluster.v2.f32 [%0], {%1,%2};" ::"r"(ra + OFF_XML + lrow * 8), "f"(M), "f"(L) : "memory");
        }
    }
    asm volatile("barrier.cluster.arrive.release.aligned;" ::: "memory");
    asm volatile("barrier.cluster.wait.acquire.aligned;" ::: "memory");
    if (owner == rank) {
        const float* xo = reinterpret_cast<const float*>(smem + OFF_XO) + lrow * 128;
        const float* xml = reinterpret_cast<const float*>(smem + OFF_XML) + lrow * 2;
        const float M2 = xml[0], L2 = xml[1];
        const float Mt = fmaxf(M, M2);
        const float f1 = ex2(M - Mt), f2 = ex2(M2 - Mt);
        const float inv = 1.0f / (L * f1 + L2 * f2);
        const float g1 = f1 * inv, g2 = f2 * inv;
        __nv_bfloat16* orow = out + ((size_t)pair * ROWS + crow) * D_;
#pragma unroll
        for (int i = 0; i < 4; i++) {
            const float4 v = *reinterpret_cast<const float4*>(xo + i * 32 + cseg * 4);
            uint2 w;
            w.x = pack_bf16(acc[4 * i] * g1 + v.x * g2, acc[4 * i + 1] * g1 + v.y * g2);
            w.y = pack_bf16(acc[4 * i + 2] * g1 + v.z * g2, acc[4 * i + 3] * g1 + v.w * g2);
            *reinterpret_cast<uint2*>(orow + i * 32 + cseg * 4) = w;
        }
    }
}

typedef CUresult (*EncodeFn)(CUtensorMap*, CUtensorMapDataType, cuuint32_t, void*, const cuuint64_t*, const cuuint64_t*,
                             const cuuint32_t*, const cuuint32_t*, CUtensorMapInterleave, CUtensorMapSwizzle,
                             CUtensorMapL2promotion, CUtensorMapFloatOOBfill);

void make_map(EncodeFn fn, CUtensorMap* map, const void* ptr) {
    cuuint64_t dims[2] = {(cuuint64_t)D_, (cuuint64_t)B_ * HKV * C_};
    cuuint64_t strides[1] = {(cuuint64_t)D_ * 2};
    cuuint32_t box[2] = {64, (cuuint32_t)R_};
    cuuint32_t estr[2] = {1, 1};
    fn(map, CU_TENSOR_MAP_DATA_TYPE_BFLOAT16, 2, const_cast<void*>(ptr), dims, strides, box, estr,
       CU_TENSOR_MAP_INTERLEAVE_NONE, CU_TENSOR_MAP_SWIZZLE_128B, CU_TENSOR_MAP_L2_PROMOTION_L2_256B,
       CU_TENSOR_MAP_FLOAT_OOB_FILL_NONE);
}

}

extern "C" void kernel_launch(void* const* d_in, const int* in_sizes, int n_in, void* d_out, int out_size) {
    (void)in_sizes; (void)n_in; (void)out_size;
    static EncodeFn encode = nullptr;
    if (!encode) {
        void* fn = nullptr;
        cudaDriverEntryPointQueryResult qres;
        cudaGetDriverEntryPoint("cuTensorMapEncodeTiled", &fn, cudaEnableDefault, &qres);
        encode = (EncodeFn)fn;
        cudaFuncSetAttribute(tree_attn_kernel, cudaFuncAttributeMaxDynamicSharedMemorySize, SMEM_BYTES);
    }
    CUtensorMap kmap, vmap;
    make_map(encode, &kmap, d_in[1]);
    make_map(encode, &vmap, d_in[2]);
    tree_attn_kernel<<<B_ * HKV * 2, NTHREADS, SMEM_BYTES>>>(
        kmap, vmap, (const __nv_bfloat16*)d_in[0], (const __nv_bfloat16*)d_in[3], (const __nv_bfloat16*)d_in[4],
        (const __nv_bfloat16*)d_in[5], (__nv_bfloat16*)d_out);
}
```

```cpp
#include <cuda_runtime.h>
#include <cuda_bf16.h>
#include <cuda.h>
#include <stdint.h>


namespace {

constexpr int B_ = 8, HQ = 32, HKV = 8, T_ = 8, C_ = 4096, D_ = 128;
constexpr int REP = HQ / HKV;
constexpr int ROWS = REP * T_;
constexpr int TK = 64;
constexpr int KEYS_PER_CTA = C_ / 2;
constexpr int NT = KEYS_PER_CTA / TK;
constexpr int STAGES = 4;
constexpr int TILE_BYTES = TK * 256;
constexpr int NTHREADS = 160;
constexpr int TREE_AT = 12;

constexpr int OFF_K = 0;
constexpr int OFF_V = OFF_K + STAGES * TILE_BYTES;
constexpr int OFF_X = OFF_V + STAGES * TILE_BYTES;
constexpr int XW_BYTES = 5 * 512;
constexpr int OFF_Q = OFF_X + 4 * XW_BYTES;
constexpr int OFF_KT = OFF_Q + ROWS * 256;
constexpr int OFF_VT = OFF_KT + T_ * 256;
constexpr int OFF_MK = OFF_VT + T_ * 256;
constexpr int OFF_BAR = OFF_MK + 128;
constexpr int SMEM_BYTES = OFF_BAR + (4 * STAGES + 3) * 8;

__device__ __forceinline__ uint32_t smem_u32(const void* p) { return (uint32_t)__cvta_generic_to_shared(p); }
__device__ __forceinline__ void mbar_init(uint32_t bar, int cnt) {
    asm volatile("mbarrier.init.shared::cta.b64 [%0], %1;" ::"r"(bar), "r"(cnt));
}
__device__ __forceinline__ void mbar_expect_tx(uint32_t bar, uint32_t bytes) {
    asm volatile("mbarrier.arrive.expect_tx.shared::cta.b64 _, [%0], %1;" ::"r"(bar), "r"(bytes) : "memory");
}
__device__ __forceinline__ void mbar_arrive(uint32_t bar) {
    asm volatile("mbarrier.arrive.shared::cta.b64 _, [%0];" ::"r"(bar) : "memory");
}
__device__ __forceinline__ bool mbar_try(uint32_t bar, uint32_t parity) {
    uint32_t ok;
    asm volatile(
        "{\n.reg .pred p;\n"
        "mbarrier.try_wait.parity.shared::cta.b64 p, [%1], %2;\n"
        "selp.u32 %0, 1, 0, p;\n}\n" : "=r"(ok) : "r"(bar), "r"(parity) : "memory");
    return ok != 0;
}
__device__ __forceinline__ void mbar_wait(uint32_t bar, uint32_t parity) {
    int it = 0;
    while (!mbar_try(bar, parity)) {
        if (++it > (1 << 22)) __trap();
    }
}
__device__ __forceinline__ void mbar_wait_cluster(uint32_t bar, uint32_t parity) {
    int it = 0;
    while (true) {
        uint32_t ok;
        asm volatile(
            "{\n.reg .pred p;\n"
            "mbarrier.try_wait.parity.acquire.cluster.shared::cta.b64 p, [%1], %2;\n"
            "selp.u32 %0, 1, 0, p;\n}\n" : "=r"(ok) : "r"(bar), "r"(parity) : "memory");
        if (ok) break;
        if (++it > (1 << 22)) __trap();
    }
}
__device__ __forceinline__ void tma_load_2d(uint32_t dst, const CUtensorMap* map, int c0, int c1, uint32_t bar) {
    asm volatile(
        "cp.async.bulk.tensor.2d.shared::cluster.global.mbarrier::complete_tx::bytes [%0], [%1, {%3, %4}], [%2];"
        ::"r"(dst), "l"(map), "r"(bar), "r"(c0), "r"(c1) : "memory");
}
__device__ __forceinline__ void bulk_load(uint32_t dst, const void* src, uint32_t bytes, uint32_t bar) {
    asm volatile("cp.async.bulk.shared::cluster.global.mbarrier::complete_tx::bytes [%0], [%1], %2, [%3];"
                 ::"r"(dst), "l"(src), "r"(bytes), "r"(bar) : "memory");
}
__device__ __forceinline__ float ex2(float x) {
    float y;
    asm("ex2.approx.ftz.f32 %0, %1;" : "=f"(y) : "f"(x));
    return y;
}
__device__ __forceinline__ float ex2v(float x) {
    float y;
    asm volatile("ex2.approx.ftz.f32 %0, %1;" : "=f"(y) : "f"(x));
    return y;
}
__device__ __forceinline__ uint32_t pack_bf16(float lo, float hi) {
    uint32_t r;
    asm("cvt.rn.bf16x2.f32 %0, %1, %2;" : "=r"(r) : "f"(hi), "f"(lo));
    return r;
}
__device__ __forceinline__ void mma16816(float& c0, float& c1, float& c2, float& c3, const uint32_t (&a)[4], uint32_t b0, uint32_t b1) {
    asm volatile(
        "mma.sync.aligned.m16n8k16.row.col.f32.bf16.bf16.f32 {%0,%1,%2,%3}, {%4,%5,%6,%7}, {%8,%9}, {%0,%1,%2,%3};"
        : "+f"(c0), "+f"(c1), "+f"(c2), "+f"(c3)
        : "r"(a[0]), "r"(a[1]), "r"(a[2]), "r"(a[3]), "r"(b0), "r"(b1));
}
__device__ __forceinline__ void wg_fence() { asm volatile("wgmma.fence.sync.aligned;" ::: "memory"); }
__device__ __forceinline__ void wg_commit() { asm volatile("wgmma.commit_group.sync.aligned;" ::: "memory"); }
__device__ __forceinline__ void wg_wait0() { asm volatile("wgmma.wait_group.sync.aligned 0;" ::: "memory"); }

__device__ __forceinline__ uint64_t make_desc(uint32_t addr, uint32_t lbo, uint32_t sbo) {
    return (uint64_t)((addr & 0x3FFFF) >> 4) | ((uint64_t)(lbo >> 4) << 16) | ((uint64_t)(sbo >> 4) << 32) | (1ull << 62);
}

__device__ __forceinline__ void wgmma_qk(float (&d)[64], const uint32_t (&a)[4], uint64_t desc, int scale_d) {
    asm volatile(
        "{\n.reg .pred p;\nsetp.ne.b32 p, %69, 0;\n"
        "wgmma.mma_async.sync.aligned.m64n128k16.f32.bf16.bf16 "
        "{%0,%1,%2,%3,%4,%5,%6,%7,%8,%9,%10,%11,%12,%13,%14,%15,%16,%17,%18,%19,%20,%21,%22,%23,%24,%25,%26,%27,%28,%29,%30,%31,"
        "%32,%33,%34,%35,%36,%37,%38,%39,%40,%41,%42,%43,%44,%45,%46,%47,%48,%49,%50,%51,%52,%53,%54,%55,%56,%57,%58,%59,%60,%61,%62,%63}, "
        "{%64,%65,%66,%67}, %68, p, 1, 1, 0;\n}\n"
        : "+f"(d[0]), "+f"(d[1]), "+f"(d[2]), "+f"(d[3]), "+f"(d[4]), "+f"(d[5]), "+f"(d[6]), "+f"(d[7]),
          "+f"(d[8]), "+f"(d[9]), "+f"(d[10]), "+f"(d[11]), "+f"(d[12]), "+f"(d[13]), "+f"(d[14]), "+f"(d[15]),
          "+f"(d[16]), "+f"(d[17]), "+f"(d[18]), "+f"(d[19]), "+f"(d[20]), "+f"(d[21]), "+f"(d[22]), "+f"(d[23]),
          "+f"(d[24]), "+f"(d[25]), "+f"(d[26]), "+f"(d[27]), "+f"(d[28]), "+f"(d[29]), "+f"(d[30]), "+f"(d[31]),
          "+f"(d[32]), "+f"(d[33]), "+f"(d[34]), "+f"(d[35]), "+f"(d[36]), "+f"(d[37]), "+f"(d[38]), "+f"(d[39]),
          "+f"(d[40]), "+f"(d[41]), "+f"(d[42]), "+f"(d[43]), "+f"(d[44]), "+f"(d[45]), "+f"(d[46]), "+f"(d[47]),
          "+f"(d[48]), "+f"(d[49]), "+f"(d[50]), "+f"(d[51]), "+f"(d[52]), "+f"(d[53]), "+f"(d[54]), "+f"(d[55]),
          "+f"(d[56]), "+f"(d[57]), "+f"(d[58]), "+f"(d[59]), "+f"(d[60]), "+f"(d[61]), "+f"(d[62]), "+f"(d[63])
        : "r"(a[0]), "r"(a[1]), "r"(a[2]), "r"(a[3]), "l"(desc), "r"(scale_d));
}
__device__ __forceinline__ void wgmma_pv(float (&d)[32], uint32_t a0, uint32_t a1, uint32_t a2, uint32_t a3, uint64_t desc) {
    asm volatile(
        "wgmma.mma_async.sync.aligned.m64n64k16.f32.bf16.bf16 "
        "{%0,%1,%2,%3,%4,%5,%6,%7,%8,%9,%10,%11,%12,%13,%14,%15,%16,%17,%18,%19,%20,%21,%22,%23,%24,%25,%26,%27,%28,%29,%30,%31}, "
        "{%32,%33,%34,%35}, %36, 1, 1, 1, 1;\n"
        : "+f"(d[0]), "+f"(d[1]), "+f"(d[2]), "+f"(d[3]), "+f"(d[4]), "+f"(d[5]), "+f"(d[6]), "+f"(d[7]),
          "+f"(d[8]), "+f"(d[9]), "+f"(d[10]), "+f"(d[11]), "+f"(d[12]), "+f"(d[13]), "+f"(d[14]), "+f"(d[15]),
          "+f"(d[16]), "+f"(d[17]), "+f"(d[18]), "+f"(d[19]), "+f"(d[20]), "+f"(d[21]), "+f"(d[22]), "+f"(d[23]),
          "+f"(d[24]), "+f"(d[25]), "+f"(d[26]), "+f"(d[27]), "+f"(d[28]), "+f"(d[29]), "+f"(d[30]), "+f"(d[31])
        : "r"(a0), "r"(a1), "r"(a2), "r"(a3), "l"(desc));
}

__global__ void __cluster_dims__(2, 1, 1) __launch_bounds__(NTHREADS, 1)
tree_attn_kernel(const __grid_constant__ CUtensorMap kmap, const __grid_constant__ CUtensorMap vmap,
                 const __nv_bfloat16* __restrict__ q, const __nv_bfloat16* __restrict__ k_tree,
                 const __nv_bfloat16* __restrict__ v_tree, const __nv_bfloat16* __restrict__ tree_mask,
                 __nv_bfloat16* __restrict__ out) {
    extern __shared__ __align__(1024) uint8_t smem[];
    const uint32_t sb = smem_u32(smem);
    const int tid = threadIdx.x, warp = tid >> 5, lane = tid & 31;
    const int pair = blockIdx.x >> 1;
    const int rank = blockIdx.x & 1;
    const int b = pair / HKV;

    const uint32_t bar_fk = sb + OFF_BAR, bar_fv = bar_fk + 8 * STAGES, bar_ek = bar_fv + 8 * STAGES,
                   bar_ev = bar_ek + 8 * STAGES, bar_x = bar_ev + 8 * STAGES, bar_q = bar_x + 8, bar_t = bar_x + 16;

    if (warp == 4) {
        const int line0 = 2 * (pair * C_ + rank * TK);
        if (lane == 0) {
            asm volatile("prefetch.tensormap [%0];" ::"l"(&kmap) : "memory");
            asm volatile("prefetch.tensormap [%0];" ::"l"(&vmap) : "memory");
#pragma unroll
            for (int s = 0; s < STAGES; s++) {
                mbar_init(bar_fk + 8 * s, 1);
                mbar_init(bar_fv + 8 * s, 1);
                mbar_init(bar_ek + 8 * s, 4);
                mbar_init(bar_ev + 8 * s, 4);
            }
            mbar_init(bar_x, 1);
            mbar_init(bar_q, 1);
            mbar_init(bar_t, 1);
            asm volatile("fence.mbarrier_init.release.cluster;" ::: "memory");
            asm volatile("fence.proxy.async.shared::cta;" ::: "memory");
        }
        __syncwarp();
        asm volatile("bar.arrive 1, 160;" ::: "memory");
        if (lane == 0) {
            mbar_expect_tx(bar_q, ROWS * 256);
            bulk_load(sb + OFF_Q, q + (size_t)pair * ROWS * D_, ROWS * 256, bar_q);
#pragma unroll
            for (int s = 0; s < STAGES; s++) {
                mbar_expect_tx(bar_fk + 8 * s, TILE_BYTES);
                tma_load_2d(sb + OFF_K + s * TILE_BYTES, &kmap, 0, line0 + s * 4 * TK, bar_fk + 8 * s);
                mbar_expect_tx(bar_fv + 8 * s, TILE_BYTES);
                tma_load_2d(sb + OFF_V + s * TILE_BYTES, &vmap, 0, line0 + s * 4 * TK, bar_fv + 8 * s);
            }
            mbar_expect_tx(bar_x, 4 * XW_BYTES);
            if (rank == 0) {
                mbar_expect_tx(bar_t, 2 * T_ * 256 + 128);
                bulk_load(sb + OFF_KT, k_tree + (size_t)pair * T_ * D_, T_ * 256, bar_t);
                bulk_load(sb + OFF_VT, v_tree + (size_t)pair * T_ * D_, T_ * 256, bar_t);
                bulk_load(sb + OFF_MK, tree_mask + b * T_ * T_, 128, bar_t);
            }
        }
        __syncwarp();
        asm volatile("barrier.cluster.arrive.relaxed.aligned;" ::: "memory");
        if (lane == 0) {
            int s = 0;
            uint32_t ph = 0;
#pragma unroll 1
            for (int j = STAGES; j < NT; j++) {
                mbar_wait(bar_ek + 8 * s, ph);
                mbar_expect_tx(bar_fk + 8 * s, TILE_BYTES);
                tma_load_2d(sb + OFF_K + s * TILE_BYTES, &kmap, 0, line0 + j * 4 * TK, bar_fk + 8 * s);
                mbar_wait(bar_ev + 8 * s, ph);
                mbar_expect_tx(bar_fv + 8 * s, TILE_BYTES);
                tma_load_2d(sb + OFF_V + s * TILE_BYTES, &vmap, 0, line0 + j * 4 * TK, bar_fv + 8 * s);
                if (++s == STAGES) { s = 0; ph ^= 1; }
            }
        }
    } else {
        const float scale = 0.08838834764831845f;
        const float log2e = 1.4426950408889634f;
        const int g = lane >> 2, qd = lane & 3;

        uint32_t qf[4][4];
        float o[32];
        float m = -INFINITY, l = 0.f;
#pragma unroll
        for (int i = 0; i < 32; i++) o[i] = 0.f;
        asm volatile("barrier.cluster.arrive.relaxed.aligned;" ::: "memory");
        asm volatile("bar.sync 1, 160;" ::: "memory");
        mbar_wait(bar_q, 0);
        {
            const uint32_t* q0 = reinterpret_cast<const uint32_t*>(smem + OFF_Q + (warp * 8 + g) * 256) + qd;
#pragma unroll
            for (int ks = 0; ks < 4; ks++) {
                qf[ks][0] = q0[ks * 8];
                qf[ks][1] = q0[32 + ks * 8];
                qf[ks][2] = q0[ks * 8 + 4];
                qf[ks][3] = q0[32 + ks * 8 + 4];
            }
        }

        const float c = scale * log2e;
        int s = 0;
        uint32_t ph = 0;
#pragma unroll 1
        for (int j = 0; j < NT; j++) {
            if (rank == 0 && j == TREE_AT) {
                mbar_wait(bar_t, 0);
                const uint32_t* kt = reinterpret_cast<const uint32_t*>(smem + OFF_KT + g * 128) + qd;
                float s0[4] = {0.f, 0.f, 0.f, 0.f}, s1[4] = {0.f, 0.f, 0.f, 0.f};
#pragma unroll
                for (int ks = 0; ks < 4; ks++) {
                    mma16816(s0[0], s0[1], s0[2], s0[3], qf[ks], kt[ks * 8], kt[ks * 8 + 4]);
                    mma16816(s1[0], s1[1], s1[2], s1[3], qf[ks], kt[256 + ks * 8], kt[256 + ks * 8 + 4]);
                }
                const __nv_bfloat16* mk = reinterpret_cast<const __nv_bfloat16*>(smem + OFF_MK) + g * T_;
                const float t0 = ((s0[0] + s0[3]) * scale + (1.0f - __bfloat162float(mk[qd])) * -1000000000.0f) * log2e;
                const float t1 = ((s1[0] + s1[3]) * scale + (1.0f - __bfloat162float(mk[4 + qd])) * -1000000000.0f) * log2e;
                float x = fmaxf(t0, t1);
                x = fmaxf(x, __shfl_xor_sync(0xffffffffu, x, 1));
                x = fmaxf(x, __shfl_xor_sync(0xffffffffu, x, 2));
                const float mn = fmaxf(m, x);
                const float al = ex2(m - mn);
                m = mn;
                const float p0 = ex2(t0 - mn), p1 = ex2(t1 - mn);
                l = l * al + (p0 + p1);
                const uint32_t pa[4] = {pack_bf16(p0, 0.f), pack_bf16(0.f, p0), pack_bf16(p1, 0.f), pack_bf16(0.f, p1)};
                const unsigned short* vt0 = reinterpret_cast<const unsigned short*>(smem + OFF_VT + 2 * qd * 128) + g;
#pragma unroll
                for (int jj = 0; jj < 8; jj++) {
                    const uint32_t b0 = (uint32_t)vt0[8 * jj] | ((uint32_t)vt0[64 + 8 * jj] << 16);
                    const uint32_t b1 = (uint32_t)vt0[512 + 8 * jj] | ((uint32_t)vt0[576 + 8 * jj] << 16);
                    o[4 * jj] *= al; o[4 * jj + 1] *= al; o[4 * jj + 2] *= al; o[4 * jj + 3] *= al;
                    mma16816(o[4 * jj], o[4 * jj + 1], o[4 * jj + 2], o[4 * jj + 3], pa, b0, b1);
                }
            }
            float sc[64];
            const uint32_t kb_ = sb + OFF_K + s * TILE_BYTES, vb_ = sb + OFF_V + s * TILE_BYTES;
            mbar_wait(bar_fk + 8 * s, ph);
            wg_fence();
#pragma unroll
            for (int ks = 0; ks < 4; ks++) wgmma_qk(sc, qf[ks], make_desc(kb_ + ks * 32, 16, 1024), ks > 0);
            wg_commit();
            wg_wait0();
            if (lane == 0) mbar_arrive(bar_ek + 8 * s);
            float sv[16];
#pragma unroll
            for (int i = 0; i < 16; i++) sv[i] = sc[4 * i] + sc[4 * i + 3];
            float x = fmaxf(fmaxf(fmaxf(fmaxf(sv[0], sv[1]), fmaxf(sv[2], sv[3])), fmaxf(fmaxf(sv[4], sv[5]), fmaxf(sv[6], sv[7]))),
                            fmaxf(fmaxf(fmaxf(sv[8], sv[9]), fmaxf(sv[10], sv[11])), fmaxf(fmaxf(sv[12], sv[13]), fmaxf(sv[14], sv[15]))));
            x = fmaxf(x, __shfl_xor_sync(0xffffffffu, x, 1));
            x = fmaxf(x, __shfl_xor_sync(0xffffffffu, x, 2));
            const float mn = fmaxf(m, x * c);
            const float al = ex2v(m - mn);
            m = mn;
            float pv_[16];
            uint32_t pa_[32];
#pragma unroll
            for (int i = 0; i < 8; i++) {
                pv_[i] = ex2v(fmaf(sv[i], c, -mn));
                pa_[2 * i] = pack_bf16(pv_[i], 0.f);
                pa_[2 * i + 1] = pa_[2 * i] << 16;
            }
#pragma unroll
            for (int i = 0; i < 32; i++) o[i] *= al;
            mbar_wait(bar_fv + 8 * s, ph);
            wg_fence();
#pragma unroll
            for (int kk = 0; kk < 4; kk++) wgmma_pv(o, pa_[4 * kk], pa_[4 * kk + 1], pa_[4 * kk + 2], pa_[4 * kk + 3], make_desc(vb_ + kk * 2048, 16, 1024));
            wg_commit();
#pragma unroll
            for (int i = 8; i < 16; i++) {
                pv_[i] = ex2v(fmaf(sv[i], c, -mn));
                pa_[2 * i] = pack_bf16(pv_[i], 0.f);
                pa_[2 * i + 1] = pa_[2 * i] << 16;
            }
            wg_fence();
#pragma unroll
            for (int kk = 4; kk < 8; kk++) wgmma_pv(o, pa_[4 * kk], pa_[4 * kk + 1], pa_[4 * kk + 2], pa_[4 * kk + 3], make_desc(vb_ + kk * 2048, 16, 1024));
            wg_commit();
            l = l * al + ((((pv_[0] + pv_[1]) + (pv_[2] + pv_[3])) + ((pv_[4] + pv_[5]) + (pv_[6] + pv_[7]))) +
                          (((pv_[8] + pv_[9]) + (pv_[10] + pv_[11])) + ((pv_[12] + pv_[13]) + (pv_[14] + pv_[15]))));
            wg_wait0();
            if (lane == 0) mbar_arrive(bar_ev + 8 * s);
            if (++s == STAGES) { s = 0; ph ^= 1; }
        }

        l += __shfl_xor_sync(0xffffffffu, l, 1);
        l += __shfl_xor_sync(0xffffffffu, l, 2);
        {
            asm volatile("barrier.cluster.wait.acquire.aligned;" ::: "memory");
            uint32_t rx, rb;
            asm volatile("mapa.shared::cluster.u32 %0, %1, %2;" : "=r"(rx) : "r"(sb + OFF_X + warp * XW_BYTES + lane * 16), "r"(rank ^ 1));
            asm volatile("mapa.shared::cluster.u32 %0, %1, %2;" : "=r"(rb) : "r"(bar_x), "r"(rank ^ 1));
            float keep[16];
#pragma unroll
            for (int i = 0; i < 4; i++) {
                float sx[4];
#pragma unroll
                for (int k = 0; k < 2; k++) {
                    sx[2 * k] = rank ? o[8 * i + 4 * k] : o[8 * i + 4 * k + 2];
                    sx[2 * k + 1] = rank ? o[8 * i + 4 * k + 1] : o[8 * i + 4 * k + 3];
                    keep[4 * i + 2 * k] = rank ? o[8 * i + 4 * k + 2] : o[8 * i + 4 * k];
                    keep[4 * i + 2 * k + 1] = rank ? o[8 * i + 4 * k + 3] : o[8 * i + 4 * k + 1];
                }
                asm volatile("st.async.shared::cluster.mbarrier::complete_tx::bytes.v4.f32 [%0], {%1,%2,%3,%4}, [%5];"
                             ::"r"(rx + i * 512), "f"(sx[0]), "f"(sx[1]), "f"(sx[2]), "f"(sx[3]), "r"(rb) : "memory");
            }
            asm volatile("st.async.shared::cluster.mbarrier::complete_tx::bytes.v4.f32 [%0], {%1,%2,%3,%4}, [%5];"
                         ::"r"(rx + 4 * 512), "f"(m), "f"(l), "f"(0.f), "f"(0.f), "r"(rb) : "memory");
            mbar_wait_cluster(bar_x, 0);
            const float4* xb = reinterpret_cast<const float4*>(smem + OFF_X + warp * XW_BYTES) + lane;
            const float4 ml = xb[4 * 32];
            const float M = fmaxf(m, ml.x);
            const float fa = ex2(m - M), fb = ex2(ml.x - M);
            const float inv = 1.0f / (l * fa + ml.y * fb);
            const float ga = fa * inv, gb = fb * inv;
            uint32_t* o0 = reinterpret_cast<uint32_t*>(out + ((size_t)pair * ROWS + warp * 8 + g) * D_ + rank * 64) + qd;
#pragma unroll
            for (int i = 0; i < 4; i++) {
                const float4 v = xb[i * 32];
                o0[8 * i] = pack_bf16(keep[4 * i] * ga + v.x * gb, keep[4 * i + 1] * ga + v.y * gb);
                o0[8 * i + 4] = pack_bf16(keep[4 * i + 2] * ga + v.z * gb, keep[4 * i + 3] * ga + v.w * gb);
            }
        }
    }
}

typedef CUresult (*EncodeFn)(CUtensorMap*, CUtensorMapDataType, cuuint32_t, void*, const cuuint64_t*, const cuuint64_t*,
                             const cuuint32_t*, const cuuint32_t*, CUtensorMapInterleave, CUtensorMapSwizzle,
                             CUtensorMapL2promotion, CUtensorMapFloatOOBfill);

void make_map(EncodeFn fn, CUtensorMap* map, const void* ptr) {
    cuuint64_t dims[2] = {64, (cuuint64_t)2 * B_ * HKV * C_};
    cuuint64_t strides[1] = {128};
    cuuint32_t box[2] = {64, (cuuint32_t)(2 * TK)};
    cuuint32_t estr[2] = {1, 1};
    fn(map, CU_TENSOR_MAP_DATA_TYPE_BFLOAT16, 2, const_cast<void*>(ptr), dims, strides, box, estr,
       CU_TENSOR_MAP_INTERLEAVE_NONE, CU_TENSOR_MAP_SWIZZLE_128B, CU_TENSOR_MAP_L2_PROMOTION_L2_256B,
       CU_TENSOR_MAP_FLOAT_OOB_FILL_NONE);
}

}

extern "C" void kernel_launch(void* const* d_in, const int* in_sizes, int n_in, void* d_out, int out_size) {
    (void)in_sizes; (void)n_in; (void)out_size;
    static EncodeFn encode = nullptr;
    if (!encode) {
        void* fn = nullptr;
        cudaDriverEntryPointQueryResult qres;
        cudaGetDriverEntryPoint("cuTensorMapEncodeTiled", &fn, cudaEnableDefault, &qres);
        encode = (EncodeFn)fn;
        cudaFuncSetAttribute(tree_attn_kernel, cudaFuncAttributeMaxDynamicSharedMemorySize, SMEM_BYTES);
    }
    CUtensorMap kmap, vmap;
    make_map(encode, &kmap, d_in[1]);
    make_map(encode, &vmap, d_in[2]);
    tree_attn_kernel<<<B_ * HKV * 2, NTHREADS, SMEM_BYTES>>>(
        kmap, vmap, (const __nv_bfloat16*)d_in[0], (const __nv_bfloat16*)d_in[3], (const __nv_bfloat16*)d_in[4],
        (const __nv_bfloat16*)d_in[5], (__nv_bfloat16*)d_out);
}
```
